```python
import torch

def _softmax(x, axis=-1):
    return torch.softmax(x, dim=axis)
def _gelu(x):
    return torch.nn.functional.gelu(x, approximate="tanh")
def _silu(x):
    return torch.nn.functional.silu(x)
def _sigmoid(x):
    return torch.sigmoid(x)
def _layernorm(x, axis=-1, eps=1e-5):
    m = x.mean(dim=axis, keepdim=True)
    v = x.var(dim=axis, keepdim=True, unbiased=False)
    return (x - m) / torch.sqrt(v + eps)
def _scatter_add(tgt, idx, src, axis=0):
    return tgt.clone().index_add_(axis, idx, src)
def _segment_sum(src, seg, n):
    out = torch.zeros((n,) + src.shape[1:], dtype=src.dtype)
    return out.index_add_(0, seg, src)
def _pad(x, pw):
    flat = tuple(v for pair in reversed(pw) for v in pair)
    return torch.nn.functional.pad(x, flat)

kernel_name = 'concat_heads__gqa_block_cached__gqa_block_cached__near_ridge'

def setup_inputs():

    _w = (lambda a: (lambda t: t.to(torch.bfloat16) if t.is_floating_point() else t)(torch.as_tensor(a)))
    def _A_setup():
        B, Sq, D = 16, 48, 512
        Hq, Hkv, Sk, Dh = 32, 8, 1024, 128
        assert Hq % Hkv == 0, (Hq, Hkv)
        return {
            "x": _w((lambda *s: torch.randn(*s, dtype=torch.bfloat16) * 0.8)(B, Sq, D)),
            "k_cache": _w((lambda *s: torch.randn(*s, dtype=torch.bfloat16) * 0.8)(B, Hkv, Sk, Dh)),
            "v_cache": _w((lambda *s: torch.randn(*s, dtype=torch.bfloat16) * 0.05)(B, Hkv, Sk, Dh)),
            "wq": _w((lambda *s: torch.randn(*s, dtype=torch.bfloat16) * 0.8)(D, Hq * Dh) * (D ** -0.5)),
            "wo": _w((lambda *s: torch.randn(*s, dtype=torch.bfloat16) * 0.05)(Hq * Dh, D) * ((Hq * Dh) ** -0.5)),
        }
    _A_in = _A_setup()

    def _B_setup():
        B, Sq, D = 16, 48, 512
        Hq, Hkv, Sk, Dh = 32, 8, 1024, 128
        assert Hq % Hkv == 0, (Hq, Hkv)
        return {
            "x": _w((lambda *s: torch.randn(*s, dtype=torch.bfloat16) * 0.8)(B, Sq, D)),
            "k_cache": _w((lambda *s: torch.randn(*s, dtype=torch.bfloat16) * 0.8)(B, Hkv, Sk, Dh)),
            "v_cache": _w((lambda *s: torch.randn(*s, dtype=torch.bfloat16) * 0.05)(B, Hkv, Sk, Dh)),
            "wq": _w((lambda *s: torch.randn(*s, dtype=torch.bfloat16) * 0.8)(D, Hq * Dh) * (D ** -0.5)),
            "wo": _w((lambda *s: torch.randn(*s, dtype=torch.bfloat16) * 0.05)(Hq * Dh, D) * ((Hq * Dh) ** -0.5)),
        }
    _B_in = _B_setup()

    return {
        "A_x": _A_in["x"],
        "A_k_cache": _A_in["k_cache"],
        "A_v_cache": _A_in["v_cache"],
        "A_wq": _A_in["wq"],
        "A_wo": _A_in["wo"],
        "B_x": _B_in["x"],
        "B_k_cache": _B_in["k_cache"],
        "B_v_cache": _B_in["v_cache"],
        "B_wq": _B_in["wq"],
        "B_wo": _B_in["wo"],
    }

def reference(A_x, A_k_cache, A_v_cache, A_wq, A_wo, B_x, B_k_cache, B_v_cache, B_wq, B_wo):
    def _A_ref(x, k_cache, v_cache, wq, wo):
        B, Sq, D = x.shape
        Hq, Dh = 32, 128
        Hkv = k_cache.shape[1]
        rep = Hq // Hkv
        q = (lambda x, *d: x.permute(*d))((x @ wq).reshape(B, Sq, Hq, Dh), 0, 2, 1, 3)
        k = (lambda x, n, axis: torch.repeat_interleave(x, n, dim=axis))(k_cache, rep, axis=1)
        v = (lambda x, n, axis: torch.repeat_interleave(x, n, dim=axis))(v_cache, rep, axis=1)
        scores = torch.einsum("bhqd,bhkd->bhqk", q, k) * (Dh ** -0.5)
        p = _softmax(scores, axis=-1)
        o = torch.einsum("bhqk,bhkd->bhqd", p, v)
        return (lambda x, *d: x.permute(*d))(o, 0, 2, 1, 3).reshape(B, Sq, Hq * Dh) @ wo

    def _B_ref(x, k_cache, v_cache, wq, wo):
        B, Sq, D = x.shape
        Hq, Dh = 32, 128
        Hkv = k_cache.shape[1]
        rep = Hq // Hkv
        q = (lambda x, *d: x.permute(*d))((x @ wq).reshape(B, Sq, Hq, Dh), 0, 2, 1, 3)
        k = (lambda x, n, axis: torch.repeat_interleave(x, n, dim=axis))(k_cache, rep, axis=1)
        v = (lambda x, n, axis: torch.repeat_interleave(x, n, dim=axis))(v_cache, rep, axis=1)
        scores = torch.einsum("bhqd,bhkd->bhqk", q, k) * (Dh ** -0.5)
        p = _softmax(scores, axis=-1)
        o = torch.einsum("bhqk,bhkd->bhqd", p, v)
        return (lambda x, *d: x.permute(*d))(o, 0, 2, 1, 3).reshape(B, Sq, Hq * Dh) @ wo

    a = _A_ref(A_x, A_k_cache, A_v_cache, A_wq, A_wo)
    b = _B_ref(B_x, B_k_cache, B_v_cache, B_wq, B_wo)
    return torch.concatenate([a, b], axis=-1)
```

```cpp
#include <cuda_runtime.h>
#include <cuda_bf16.h>
#include <cuda.h>
#include <stdint.h>

namespace {
constexpr uint32_t PF_BYTES = 4096;
constexpr uint32_t PF_DT    = 190;
constexpr uint32_t PACE_T0  = 8200;
constexpr uint32_t PACE_DT  = 1195;
constexpr uint32_t PACE_STG = 75;

constexpr int UNIT       = 16384;
constexpr int X_BYTES    = 98304;
constexpr int HALF       = 49152;
constexpr int OFF_RING   = X_BYTES;
constexpr int OFF_FULL   = X_BYTES + 8 * UNIT;
constexpr int OFF_EMPTY  = OFF_FULL + 64;
constexpr int OFF_LAST   = OFF_EMPTY + 64;
constexpr int OFF_XFULL  = OFF_LAST + 64;
constexpr int OFF_OWN    = OFF_XFULL + 32;
constexpr int OFF_TAG    = OFF_OWN + 8;
constexpr int SMEM_BYTES = OFF_TAG + 8 + 1024;
constexpr int NTHREADS   = 512;
constexpr unsigned SPIN_LIMIT = 1u << 18;

struct Params {
    CUtensorMap x[2], k[2], v[2], wq[2], wo[2];
    const uint8_t* kp[2];
    const uint8_t* vp[2];
};

__device__ uint4 g_part[2 * 8 * 8 * 8 * 6 * 128];
__device__ unsigned g_epoch[128];

__device__ __forceinline__ uint32_t smem_u32(const void* p) { return (uint32_t)__cvta_generic_to_shared(p); }
__device__ __forceinline__ void mbar_init(uint32_t a, uint32_t c) {
    asm volatile("mbarrier.init.shared::cta.b64 [%0], %1;" ::"r"(a), "r"(c) : "memory");
}
__device__ __forceinline__ void mbar_expect_tx(uint32_t a, uint32_t b) {
    asm volatile("mbarrier.arrive.expect_tx.shared::cta.b64 _, [%0], %1;" ::"r"(a), "r"(b) : "memory");
}
__device__ __forceinline__ bool mbar_try(uint32_t a, uint32_t ph) {
    uint32_t ok;
    asm volatile("{\n.reg .pred p;\nmbarrier.try_wait.parity.shared::cta.b64 p, [%1], %2;\nselp.u32 %0, 1, 0, p;\n}"
                 : "=r"(ok) : "r"(a), "r"(ph) : "memory");
    return ok != 0;
}
__device__ __forceinline__ bool mbar_test(uint32_t a, uint32_t ph) {
    uint32_t ok;
    asm volatile("{\n.reg .pred p;\nmbarrier.test_wait.parity.shared::cta.b64 p, [%1], %2;\nselp.u32 %0, 1, 0, p;\n}"
                 : "=r"(ok) : "r"(a), "r"(ph) : "memory");
    return ok != 0;
}
__device__ __forceinline__ void mbar_wait(uint32_t a, uint32_t ph) {
    unsigned n = 0;
    while (!mbar_try(a, ph)) { if (++n > SPIN_LIMIT) break; }
}
__device__ __forceinline__ void mbar_arrive_cnt(uint32_t a, uint32_t cnt) {
    asm volatile("mbarrier.arrive.shared::cta.b64 _, [%0], %1;" ::"r"(a), "r"(cnt) : "memory");
}
__device__ __forceinline__ void mbar_arrive_remote(uint32_t a, uint32_t cta, uint32_t cnt) {
    asm volatile("{\n.reg .b32 r;\nmapa.shared::cluster.u32 r, %0, %1;\n"
                 "mbarrier.arrive.shared::cluster.b64 _, [r], %2;\n}" ::"r"(a), "r"(cta), "r"(cnt) : "memory");
}
__device__ __forceinline__ void tma3d(uint32_t dst, const CUtensorMap* m, int c0, int c1, int c2, uint32_t bar) {
    asm volatile("cp.async.bulk.tensor.3d.shared::cluster.global.mbarrier::complete_tx::bytes [%0], [%1, {%3, %4, %5}], [%2];"
                 ::"r"(dst), "l"(m), "r"(bar), "r"(c0), "r"(c1), "r"(c2) : "memory");
}
__device__ __forceinline__ void tma3d_hint(uint32_t dst, const CUtensorMap* m, int c0, int c1, int c2, uint32_t bar, uint64_t pol) {
    asm volatile("cp.async.bulk.tensor.3d.shared::cluster.global.mbarrier::complete_tx::bytes.L2::cache_hint [%0], [%1, {%3, %4, %5}], [%2], %6;"
                 ::"r"(dst), "l"(m), "r"(bar), "r"(c0), "r"(c1), "r"(c2), "l"(pol) : "memory");
}
__device__ __forceinline__ void tma3d_mc(uint32_t dst, const CUtensorMap* m, int c0, int c1, int c2, uint32_t bar, uint16_t mask) {
    asm volatile("cp.async.bulk.tensor.3d.shared::cluster.global.mbarrier::complete_tx::bytes.multicast::cluster [%0], [%1, {%3, %4, %5}], [%2], %6;"
                 ::"r"(dst), "l"(m), "r"(bar), "r"(c0), "r"(c1), "r"(c2), "h"(mask) : "memory");
}
__device__ __forceinline__ void bar_sync(int id, int n) { asm volatile("bar.sync %0, %1;" ::"r"(id), "r"(n) : "memory"); }
__device__ __forceinline__ void bar_arrive(int id, int n) { asm volatile("bar.arrive %0, %1;" ::"r"(id), "r"(n) : "memory"); }
__device__ __forceinline__ void fence_async_smem() { asm volatile("fence.proxy.async.shared::cta;" ::: "memory"); }
__device__ __forceinline__ void wg_fence() { asm volatile("wgmma.fence.sync.aligned;" ::: "memory"); }
__device__ __forceinline__ void wg_commit() { asm volatile("wgmma.commit_group.sync.aligned;" ::: "memory"); }
template <int N> __device__ __forceinline__ void wg_wait() { asm volatile("wgmma.wait_group.sync.aligned %0;" ::"n"(N) : "memory"); }
__device__ __forceinline__ float ex2(float x) { float y; asm("ex2.approx.ftz.f32 %0, %1;" : "=f"(y) : "f"(x)); return y; }
__device__ __forceinline__ uint32_t pack_bf16(float lo, float hi) {
    uint32_t r; asm("cvt.rn.bf16x2.f32 %0, %1, %2;" : "=r"(r) : "f"(hi), "f"(lo)); return r;
}
__device__ __forceinline__ void stsm4(uint32_t a, uint32_t r0, uint32_t r1, uint32_t r2, uint32_t r3) {
    asm volatile("stmatrix.sync.aligned.m8n8.x4.shared.b16 [%0], {%1, %2, %3, %4};" ::"r"(a), "r"(r0), "r"(r1), "r"(r2), "r"(r3) : "memory");
}
__device__ __forceinline__ void stsm4t(uint32_t a, uint32_t r0, uint32_t r1, uint32_t r2, uint32_t r3) {
    asm volatile("stmatrix.sync.aligned.m8n8.x4.trans.shared.b16 [%0], {%1, %2, %3, %4};" ::"r"(a), "r"(r0), "r"(r1), "r"(r2), "r"(r3) : "memory");
}
__device__ __forceinline__ uint32_t gtime() { uint32_t t; asm volatile("mov.u32 %0, %%globaltimer_lo;" : "=r"(t)); return t; }
__device__ __forceinline__ void l2_prefetch(const void* p, uint32_t bytes) {
    asm volatile("cp.async.bulk.prefetch.L2.global [%0], %1;" ::"l"(p), "r"(bytes) : "memory");
}
__device__ __forceinline__ void tma3d_prefetch(const CUtensorMap* m, int c0, int c1, int c2) {
    asm volatile("cp.async.bulk.prefetch.tensor.3d.L2.global [%0, {%1, %2, %3}];" ::"l"(m), "r"(c0), "r"(c1), "r"(c2) : "memory");
}
__device__ __forceinline__ uint32_t desc_k(uint32_t a) { return ((a & 0x3FFFF) >> 4) | (1u << 16); }
__device__ __forceinline__ uint32_t desc_mn(uint32_t a) { return ((a & 0x3FFFF) >> 4) | (1024u << 16); }

#define ACC8(d, i) "+f"(d[i]), "+f"(d[i + 1]), "+f"(d[i + 2]), "+f"(d[i + 3]), "+f"(d[i + 4]), "+f"(d[i + 5]), "+f"(d[i + 6]), "+f"(d[i + 7])
#define ACC48(d) ACC8(d, 0), ACC8(d, 8), ACC8(d, 16), ACC8(d, 24), ACC8(d, 32), ACC8(d, 40)
#define ACC64(d) ACC48(d), ACC8(d, 48), ACC8(d, 56)
#define OUT8(d, i) "=f"(d[i]), "=f"(d[i + 1]), "=f"(d[i + 2]), "=f"(d[i + 3]), "=f"(d[i + 4]), "=f"(d[i + 5]), "=f"(d[i + 6]), "=f"(d[i + 7])
#define OUT48(d) OUT8(d, 0), OUT8(d, 8), OUT8(d, 16), OUT8(d, 24), OUT8(d, 32), OUT8(d, 40)
#define OUT64(d) OUT48(d), OUT8(d, 48), OUT8(d, 56)
#define REGS48_                                                                                  \
    "{%0, %1, %2, %3, %4, %5, %6, %7, %8, %9, %10, %11, %12, %13, %14, %15, "                    \
    "%16, %17, %18, %19, %20, %21, %22, %23, %24, %25, %26, %27, %28, %29, %30, %31, "           \
    "%32, %33, %34, %35, %36, %37, %38, %39, %40, %41, %42, %43, %44, %45, %46, %47"
#define REGS48 REGS48_ "}"
#define REGS64 REGS48_ ", %48, %49, %50, %51, %52, %53, %54, %55, %56, %57, %58, %59, %60, %61, %62, %63}"

template <int OA, int OB, int ACC>
__device__ __forceinline__ void wgmma_qk(float (&d)[64], uint32_t da, uint32_t db) {
#define WGMMA_QK_BODY                                                                              \
    "{\n.reg .b32 la, lb;\n.reg .b64 da, db;\n"                                                    \
    "add.u32 la, %64, %66;\nadd.u32 lb, %65, %67;\n"                                               \
    "mov.b64 da, {la, 0x40000080};\nmov.b64 db, {lb, 0x40000040};\n"                               \
    "wgmma.mma_async.sync.aligned.m64n128k16.f32.bf16.bf16 " REGS64 ", da, db, %68, 1, 1, 0, 0;\n}"
    if constexpr (ACC)
        asm volatile(WGMMA_QK_BODY : ACC64(d) : "r"(da), "r"(db), "n"(OA >> 4), "n"(OB >> 4), "n"(1));
    else
        asm volatile(WGMMA_QK_BODY : OUT64(d) : "r"(da), "r"(db), "n"(OA >> 4), "n"(OB >> 4), "n"(0));
}
template <int OB>
__device__ __forceinline__ void wgmma_pv(float (&d)[64], uint32_t a0, uint32_t a1, uint32_t a2, uint32_t a3, uint32_t db) {
    asm volatile("{\n.reg .b32 lb;\n.reg .b64 db;\n"
                 "add.u32 lb, %68, %69;\nmov.b64 db, {lb, 0x40000040};\n"
                 "wgmma.mma_async.sync.aligned.m64n128k16.f32.bf16.bf16 " REGS64 ", {%64, %65, %66, %67}, db, 1, 1, 1, 1;\n}"
                 : ACC64(d) : "r"(a0), "r"(a1), "r"(a2), "r"(a3), "r"(db), "n"(OB >> 4));
}
template <int OA, int OB, int ACC>
__device__ __forceinline__ void wgmma_w(float (&d)[48], uint32_t da, uint32_t db) {
#define WGMMA_W_BODY                                                                               \
    "{\n.reg .b32 la, lb;\n.reg .b64 da, db;\n"                                                    \
    "add.u32 la, %48, %50;\nadd.u32 lb, %49, %51;\n"                                               \
    "mov.b64 da, {la, 0x40000040};\nmov.b64 db, {lb, 0x40000040};\n"                               \
    "wgmma.mma_async.sync.aligned.m64n96k16.f32.bf16.bf16 " REGS48 ", da, db, %52, 1, 1, 1, 0;\n}"
    if constexpr (ACC)
        asm volatile(WGMMA_W_BODY : ACC48(d) : "r"(da), "r"(db), "n"(OA >> 4), "n"(OB >> 4), "n"(1));
    else
        asm volatile(WGMMA_W_BODY : OUT48(d) : "r"(da), "r"(db), "n"(OA >> 4), "n"(OB >> 4), "n"(0));
}
__device__ __forceinline__ void pin64(float (&d)[64]) { asm volatile("" : ACC64(d) :: "memory"); }
template <int N> struct IC { static constexpr int v = N; };
template <class F> __device__ __forceinline__ void for8(F f) {
    f(IC<0>{}); f(IC<1>{}); f(IC<2>{}); f(IC<3>{}); f(IC<4>{}); f(IC<5>{}); f(IC<6>{}); f(IC<7>{});
}
template <class F> __device__ __forceinline__ void for4(F f) { f(IC<0>{}); f(IC<1>{}); f(IC<2>{}); f(IC<3>{}); }

__device__ __forceinline__ void release(uint32_t bar, bool next_mc, uint32_t cnt, uint32_t peer) {
    if (next_mc) { mbar_arrive_cnt(bar, cnt); mbar_arrive_remote(bar, peer, cnt); }
    else mbar_arrive_cnt(bar, 2 * cnt);
}

template <int OPROJ> __host__ __device__ constexpr int boff(int s) {
    return OPROJ ? ((s >> 2) & 1) * HALF + (s >> 3) * 12288 + (s & 3) * 32 : (s >> 2) * 12288 + (s & 3) * 32;
}
template <int OPROJ>
__device__ __forceinline__ void gemm_tile(float (&acc)[48], uint32_t sb, int ti, int lane, uint32_t peer, bool first) {
    const uint32_t db = desc_k(sb);
    const uint32_t da = desc_mn(sb + OFF_RING + (ti & 1) * 4 * UNIT);
    const uint32_t fb = sb + OFF_FULL + (ti & 1) * 32, ph = (ti >> 1) & 1;
    const bool rel = (lane == 0) && !(OPROJ && ti >= 6), mc = OPROJ || ti < 6;
    for4([&](auto U) {
        constexpr int u = decltype(U)::v;
        if (!OPROJ && first) mbar_wait(sb + OFF_XFULL + u * 8, 0);
        if (OPROJ && first && u < 3) bar_sync(8 + u, u ? 256 : 128);
        mbar_wait(fb + u * 8, ph);
        wg_fence();
        for8([&](auto S) {
            constexpr int s = decltype(S)::v;
            wgmma_w<u * UNIT + s * 2048, boff<OPROJ>(u * 8 + s), (u != 0 || s != 0)>(acc, da, db);
        });
        wg_commit();
        if (OPROJ && u == 3 && first) bar_arrive(4, 256);
        if (u > 0) { wg_wait<1>(); if (rel) release(fb + 56 + u * 8, mc, 3, peer); }
    });
    wg_wait<0>();
    if (rel) release(fb + 64 + 24, mc, 3, peer);
}

constexpr int NCHUNK = 3;
__host__ __device__ constexpr int chb(int c) { return (0x8740 >> (4 * c)) & 15; }
constexpr float CS = 0.08838834764831845f * 1.4426950408889634f;
__device__ __forceinline__ void softmax_max(const float (&s)[64], float (&o)[64], float& m0, float& m1, float& l0, float& l1) {
    float x0, x1;
    int y[4];
#pragma unroll
    for (int c = 0; c < 4; c++) y[c] = max(__float_as_int(s[(c >> 1) * 4 + (c & 1) * 2]), __float_as_int(s[(c >> 1) * 4 + (c & 1) * 2 + 1]));
#pragma unroll
    for (int j = 1; j < 8; j++)
#pragma unroll
        for (int c = 0; c < 4; c++)
            y[c] = __vimax3_s32(y[c], __float_as_int(s[8 * j + (c >> 1) * 4 + (c & 1) * 2]), __float_as_int(s[8 * j + (c >> 1) * 4 + (c & 1) * 2 + 1]));
    y[0] = max(y[0], y[2]); y[1] = max(y[1], y[3]);
    x0 = __int_as_float(y[0]); x1 = __int_as_float(y[1]);
    if (__any_sync(0xffffffffu, (y[0] | y[1]) < 0)) {
        x0 = fmaxf(s[0], s[1]); x1 = fmaxf(s[2], s[3]);
        float x2 = fmaxf(s[4], s[5]), x3 = fmaxf(s[6], s[7]);
#pragma unroll
        for (int j = 8; j < 64; j += 4) {
            x0 = fmaxf(x0, s[j]); x1 = fmaxf(x1, s[j + 2]); x2 = fmaxf(x2, s[j + 1]); x3 = fmaxf(x3, s[j + 3]);
        }
        x0 = fmaxf(x0, x2); x1 = fmaxf(x1, x3);
    }
    x0 = fmaxf(x0, __shfl_xor_sync(0xffffffffu, x0, 1));
    x1 = fmaxf(x1, __shfl_xor_sync(0xffffffffu, x1, 1));
    x0 = fmaxf(x0, __shfl_xor_sync(0xffffffffu, x0, 2));
    x1 = fmaxf(x1, __shfl_xor_sync(0xffffffffu, x1, 2));
    x0 = fmaxf(x0, m0); x1 = fmaxf(x1, m1);
    const float a0 = ex2((m0 - x0) * CS), a1 = ex2((m1 - x1) * CS);
    m0 = x0; m1 = x1;
    l0 *= a0; l1 *= a1;
#pragma unroll
    for (int j = 0; j < 64; j++) o[j] *= (j & 2) ? a1 : a0;
}
template <int J0, int J1>
__device__ __forceinline__ void softmax_exp(const float (&s)[64], uint32_t (&p)[32], float n0, float n1, float& l0, float& l1) {
    float r0 = 0.f, r1 = 0.f;
#pragma unroll
    for (int j = J0; j < J1; j += 4) {
        const float e0 = ex2(fmaf(s[j], CS, n0)), e1 = ex2(fmaf(s[j + 1], CS, n0));
        const float e2 = ex2(fmaf(s[j + 2], CS, n1)), e3 = ex2(fmaf(s[j + 3], CS, n1));
        p[j >> 1] = pack_bf16(e0, e1); p[(j >> 1) + 1] = pack_bf16(e2, e3);
        if (j == J0) { r0 = e1; r1 = e3; } else { r0 += e1; r1 += e3; }
        l0 += e0; l1 += e2;
    }
    l0 += r0; l1 += r1;
}


__device__ __forceinline__ void pack48(const float (&a)[48], uint32_t (&p)[24]) {
#pragma unroll
    for (int j = 0; j < 24; j++) p[j] = pack_bf16(a[2 * j], a[2 * j + 1]);
}
__device__ __forceinline__ void store_q(uint32_t sb, int mt, int wl, int lane, const uint32_t (&p)[24]) {
    const int i = lane & 7, mh = (lane >> 3) & 1, jo = lane >> 4;
    const uint32_t base = sb + (mt & 1) * HALF + (mt >> 1) * 12288 + jo * 2048 + i * 128 + (((wl * 2 + mh) ^ i) << 4);
#pragma unroll
    for (int j = 0; j < 12; j += 2)
        stsm4t(base + (j % 6) * 2048 + (j / 6) * 1024, p[2 * j], p[2 * j + 1], p[2 * j + 2], p[2 * j + 3]);
}
__device__ __forceinline__ void ld_part(uint32_t (&v)[24], const uint4* p) {
#pragma unroll
    for (int j = 0; j < 6; j++)
        asm volatile("{\n.reg .b128 q;\nld.relaxed.gpu.global.b128 q, [%4];\nmov.b128 {%0, %1, %2, %3}, q;\n}"
                     : "=r"(v[4 * j]), "=r"(v[4 * j + 1]), "=r"(v[4 * j + 2]), "=r"(v[4 * j + 3]) : "l"(p + j * 128) : "memory");
}
__device__ __forceinline__ bool add_part(float (&acc)[48], const uint32_t (&v)[24], uint32_t tag) {
    uint32_t bad = 0;
#pragma unroll
    for (int j = 0; j < 24; j += 4) bad |= v[j] ^ tag;
    if (!__all_sync(0xffffffffu, (bad & 1) == 0)) return false;
#pragma unroll
    for (int j = 0; j < 24; j++) { acc[2 * j] += __uint_as_float(v[j] << 16); acc[2 * j + 1] += __uint_as_float(v[j] & 0xffff0000u); }
    return true;
}

__global__ void __cluster_dims__(2, 1, 1) __launch_bounds__(NTHREADS, 1)
gqa_fused_kernel(const __grid_constant__ Params P, __nv_bfloat16* __restrict__ out) {
    extern __shared__ uint8_t smem_raw[];
    const uint32_t sb = (smem_u32(smem_raw) + 1023) & ~1023u;
    const int tid = threadIdx.x, lane = tid & 31;
    const int warp = __shfl_sync(0xffffffffu, tid >> 5, 0), wg = warp >> 2;
    const uint32_t rank = blockIdx.x & 1, peer = rank ^ 1;
    const int hkv = (blockIdx.x >> 1) & 7, bp = ((blockIdx.x >> 4) & 3) * 2 + rank, br = blockIdx.x >> 6;

    const int gi = (bp >> 1) * 2 + br;
    uint32_t tnext = gtime() + PACE_T0 + gi * PACE_STG;
    if (wg == 3) asm volatile("setmaxnreg.dec.sync.aligned.u32 32;");
    if (warp >= 12) {
        if (lane == 0) {
            mbar_init(sb + OFF_XFULL + (warp - 12) * 8, 1);
            mbar_expect_tx(sb + OFF_XFULL + (warp - 12) * 8, X_BYTES / 4);
            asm volatile("fence.mbarrier_init.release.cluster;" ::: "memory");
            if (warp == 12) tma3d(sb, &P.x[br], 0, bp * 96, 0, sb + OFF_XFULL);
        }
    } else if (warp < 8 && lane == 0) {
        mbar_init(sb + OFF_FULL + warp * 8, 1);
        mbar_init(sb + OFF_EMPTY + warp * 8, 24);
        mbar_expect_tx(sb + OFF_FULL + warp * 8, UNIT);
        asm volatile("fence.mbarrier_init.release.cluster;" ::: "memory");
    } else if (warp < 12 && lane == 0) {
        mbar_init(sb + OFF_LAST + (warp - 8) * 16, 24);
        if (warp == 8) mbar_init(sb + OFF_OWN, 128);
        asm volatile("fence.mbarrier_init.release.cluster;" ::: "memory");
    }
    __syncwarp();
    asm volatile("barrier.cluster.arrive.relaxed.aligned;\nbarrier.cluster.wait.aligned;" ::: "memory");
    if (warp == 12 && lane == 0) {
#pragma unroll
        for (int q = 0; q < 4; q++) {
            if (q > 0) tma3d(sb + q * (X_BYTES / 4), &P.x[br], 0, bp * 96, q * 2, sb + OFF_XFULL + q * 8);
            if ((q & 1) == rank) {
                tma3d_mc(sb + OFF_RING + q * UNIT, &P.wq[br], 0, q * 128, hkv * 8, sb + OFF_FULL + q * 8, 3);
                tma3d_mc(sb + OFF_RING + (q + 4) * UNIT, &P.wq[br], 0, q * 128, hkv * 8 + 1, sb + OFF_FULL + (q + 4) * 8, 3);
            }
        }
#pragma unroll
        for (int q = 1; q < 4; q++) tma3d_prefetch(&P.wq[br], 0, (bp >> 1) * 128, hkv * 8 + q * 2 + rank);
    }
    __syncwarp();

    if (wg == 3) {
        if (warp == 12 && lane == 0) {
            uint64_t pol;
            asm volatile("createpolicy.fractional.L2::evict_first.b64 %0, 1.0;" : "=l"(pol));
#pragma unroll 1
            for (int i = 8; i < 32; i++) {
                const int u = i & 7, r = i >> 3;
                mbar_wait(sb + OFF_EMPTY + u * 8, (r - 1) & 1);
                mbar_expect_tx(sb + OFF_FULL + u * 8, UNIT);
                if ((i & 1) == rank) tma3d_mc(sb + OFF_RING + u * UNIT, &P.wq[br], 0, (i & 3) * 128, hkv * 8 + (i >> 2), sb + OFF_FULL + u * 8, 3);
            }
#pragma unroll 1
            for (int j = 0; j < 32; j++) {
                const int u = (j & 3) * 2, r = 4 + (j >> 2);
                mbar_wait(sb + OFF_EMPTY + u * 8, (r - 1) & 1);
                if (r == 4) mbar_wait(sb + OFF_EMPTY + u * 8 + 8, 1);
                for (int n = 0; n < 4096 && (int)(gtime() - tnext) < 0; n++) {}
                tnext += PACE_DT + (uint32_t)((2 * gi - 7) * 40 / 64);
                mbar_expect_tx(sb + OFF_FULL + u * 8, 2 * UNIT);
                tma3d_hint(sb + OFF_RING + u * UNIT, (j & 1) ? &P.v[br] : &P.k[br], 0,
                           ((bp * 2 + (j >> 4)) * 8 + hkv) * 1024 + ((j >> 1) & 7) * 128, 0, sb + OFF_FULL + u * 8, pol);
            }
#pragma unroll 1
            for (int i = 0; i < 32; i++) {
                const int u = i & 7, r = 12 + (i >> 3);
                if (r == 12) mbar_wait(sb + OFF_LAST + (u >> 1) * 16, 0);
                else mbar_wait(sb + OFF_EMPTY + u * 8, (r + u) & 1);
                mbar_expect_tx(sb + OFF_FULL + u * 8, UNIT);
                if ((i & 1) == rank) tma3d_mc(sb + OFF_RING + u * UNIT, &P.wo[br], 0, hkv * 512 + (i & 3) * 128, (hkv + 1 + (i >> 2)) & 7, sb + OFF_FULL + u * 8, 3);
            }
        } else if (warp == 14) {
            mbar_wait(sb + OFF_XFULL + 24, 0);
            const uint8_t* base = ((lane & 1) ? P.vp[br] : P.kp[br]) + (size_t)(((bp * 2 + (lane >> 4)) * 8 + hkv) * 1024 + ((lane >> 1) & 7) * 128) * 256;
            uint32_t tp = gtime();
#pragma unroll 1
            for (int q = 0; q < 32; q++) {
                if (lane == q) l2_prefetch(base, PF_BYTES);
                tp += PF_DT;
                for (int n = 0; n < 256 && (int)(gtime() - tp) < 0; n++) __nanosleep(20);
            }
        }
    } else {
        asm volatile("setmaxnreg.inc.sync.aligned.u32 160;");
        const int wl = warp & 3;
        {
            if (wg < 2) {
                float acc[48];
                uint32_t q0[24], q1[24], q2[24];
                gemm_tile<0>(acc, sb, wg, lane, peer, true);
                pack48(acc, q0);
                gemm_tile<0>(acc, sb, wg + 2, lane, peer, false);
                pack48(acc, q1);
                gemm_tile<0>(acc, sb, wg + 4, lane, peer, false);
                pack48(acc, q2);
                gemm_tile<0>(acc, sb, wg + 6, lane, peer, false);
                bar_sync(2, 256);
                store_q(sb, wg, wl, lane, q0);
                store_q(sb, wg + 2, wl, lane, q1);
                store_q(sb, wg + 4, wl, lane, q2);
                pack48(acc, q0);
                store_q(sb, wg + 6, wl, lane, q0);
            } else if (tid == 256) {
                const uint32_t e = *(volatile unsigned*)&g_epoch[blockIdx.x] ^ 1u;
                asm volatile("st.shared.u32 [%0], %1;" ::"r"(sb + OFF_TAG), "r"(e) : "memory");
                g_epoch[blockIdx.x] = e;
            }
            fence_async_smem();
            bar_sync(1, 384);
        }
        if (wg == 2) bar_arrive(5, 256);
        {
            float o[64], s[64];
#pragma unroll
            for (int j = 0; j < 64; j++) o[j] = 0.f;
            float m0 = -INFINITY, m1 = -INFINITY, l0 = 0.f, l1 = 0.f;
            auto wait_k = [&](int t) {
                mbar_wait(sb + OFF_FULL + (t & 1) * 32, (t >> 1) & 1);
                bar_sync(5 + wg, 256);
            };
            auto issue_qk = [&](int t) {
                const uint32_t dq = desc_k(sb + wg * 16384 + (t >> 3) * 1024), dk = desc_k(sb + OFF_RING + (t & 1) * 4 * UNIT);
                for8([&](auto KK) {
                    constexpr int kk = decltype(KK)::v;
                    wgmma_qk<(kk >> 2) * HALF + (kk & 3) * 32, (kk >> 2) * 16384 + (kk & 3) * 32, kk != 0>(s, dq, dk);
                });
                wg_commit();
            };
            auto done_qk = [&](int t) {
                if (!(wg == 2 && t == 15)) bar_arrive(5 + (wg == 2 ? 0 : wg + 1), 256);
                if (lane == 0) release(sb + OFF_FULL + (t & 1) * 32 + (t >= 14 ? 128 : 64), t >= 14, 1, peer);
            };
            auto store_o = [&](int bb) {
                l0 += __shfl_xor_sync(0xffffffffu, l0, 1); l1 += __shfl_xor_sync(0xffffffffu, l1, 1);
                l0 += __shfl_xor_sync(0xffffffffu, l0, 2); l1 += __shfl_xor_sync(0xffffffffu, l1, 2);
                const float r0 = 1.f / l0, r1 = 1.f / l1;
                const uint32_t base = sb + wg * 16384 + wl * 4096 + bb * 1024 + ((lane >> 3) & 1) * 2048 + (lane & 7) * 128;
#pragma unroll
                for (int j = 0; j < 16; j += 2) {
                    const int ch = ((j & 7) + (lane >> 4)) ^ (lane & 7);
                    stsm4(base + (j >> 3) * HALF + ch * 16,
                          pack_bf16(o[4 * j] * r0, o[4 * j + 1] * r0), pack_bf16(o[4 * j + 2] * r1, o[4 * j + 3] * r1),
                          pack_bf16(o[4 * j + 4] * r0, o[4 * j + 5] * r0), pack_bf16(o[4 * j + 6] * r1, o[4 * j + 7] * r1));
                }
            };
            wait_k(0);
            wg_fence();
            issue_qk(0);
            wg_wait<0>();
            pin64(s);
            done_qk(0);
#pragma unroll 1
            for (int t = 0;; t++) {
                const uint32_t fb = sb + OFF_FULL + (t & 1) * 32;
                uint32_t p[32];
                softmax_max(s, o, m0, m1, l0, l1);
                const float n0 = -m0 * CS, n1 = -m1 * CS;
                const uint32_t dv = desc_mn(sb + OFF_RING + (t & 1) * 4 * UNIT + 2 * UNIT);
                auto issue_pv = [&](auto C) {
                    constexpr int c = decltype(C)::v;
                    wg_fence();
                    for8([&](auto KK) {
                        constexpr int kk = decltype(KK)::v;
                        if constexpr (kk >= chb(c) && kk < chb(c + 1)) wgmma_pv<kk * 2048>(o, p[4 * kk], p[4 * kk + 1], p[4 * kk + 2], p[4 * kk + 3], dv);
                    });
                    wg_commit();
                };
                for8([&](auto C) {
                    constexpr int c = decltype(C)::v;
                    if constexpr (c < NCHUNK) {
                        softmax_exp<chb(c) * 8, chb(c + 1) * 8>(s, p, n0, n1, l0, l1);
                        if (c == 0) mbar_wait(fb + 16, (t >> 1) & 1);
                        if constexpr (c + 1 < NCHUNK) issue_pv(C);
                    }
                });
                wg_wait<0>();
                pin64(o);
                const uint32_t ve = fb + (t >= 14 ? 144 : 80);
                if (t == 15) {
                    issue_pv(IC<NCHUNK - 1>{});
                    wg_wait<0>();
                    pin64(o);
                    if (lane == 0) release(ve, true, 1, peer);
                    break;
                }
                wait_k(t + 1);
                issue_pv(IC<NCHUNK - 1>{});
                issue_qk(t + 1);
                wg_wait<1>();
                if (lane == 0) release(ve, t >= 14, 1, peer);
                wg_wait<0>();
                pin64(o); pin64(s);
                done_qk(t + 1);
                if (t == 7) {
                    store_o(0);
#pragma unroll
                    for (int j = 0; j < 64; j++) o[j] = 0.f;
                    m0 = m1 = -INFINITY; l0 = l1 = 0.f;
                }
            }
            store_o(1);
        }
        uint32_t tag;
        asm volatile("ld.shared.u32 %0, [%1];" : "=r"(tag) : "r"(sb + OFF_TAG) : "memory");
        fence_async_smem();
        if (wg > 0) bar_arrive(8 + wg, 256);
        float acc[48];
        const int grp = (br * 8 + bp) * 8;
        const uint32_t own = sb + OFF_RING + 5 * UNIT + (tid & 127) * 16;
        if (wg < 2) {
            auto put = [&](const float (&c)[48], int s) {
                uint4* dst = g_part + (size_t)((grp + ((hkv + 1 + s) & 7)) * 8 + hkv) * 768 + (tid & 127);
#pragma unroll
                for (int j = 0; j < 6; j++)
                    asm volatile("{\n.reg .b128 q;\nmov.b128 q, {%1, %2, %3, %4};\nst.relaxed.gpu.global.b128 [%0], q;\n}"
                                 ::"l"(dst + j * 128), "r"((pack_bf16(c[8 * j], c[8 * j + 1]) & ~1u) | tag), "r"(pack_bf16(c[8 * j + 2], c[8 * j + 3])),
                                 "r"(pack_bf16(c[8 * j + 4], c[8 * j + 5])), "r"(pack_bf16(c[8 * j + 6], c[8 * j + 7])) : "memory");
            };
#pragma unroll 1
            for (int s = wg; s < 8; s += 2) {
                if (s == 1) bar_sync(4, 256);
                gemm_tile<1>(acc, sb, s, lane, peer, s == 0);
                if (s == 7) break;
                put(acc, s);
            }
            if (wg == 1) {
                bar_sync(3, 128);
#pragma unroll
                for (int j = 0; j < 12; j++)
                    asm volatile("st.shared.v4.f32 [%0], {%1, %2, %3, %4};" ::"r"(own + j * 2048),
                                 "f"(acc[4 * j]), "f"(acc[4 * j + 1]), "f"(acc[4 * j + 2]), "f"(acc[4 * j + 3]) : "memory");
                mbar_arrive_cnt(sb + OFF_OWN, 1);
            }
        } else {
#pragma unroll
            for (int j = 0; j < 48; j++) acc[j] = 0.f;
            unsigned n = 0, pending = 0xffu & ~(1u << hkv), ready = 0;
            bool own_done = false;
            const uint4* src = g_part + (size_t)(grp + hkv) * 8 * 768 + (tid & 127);
            const unsigned* poll = &(src - lane + 31 + (lane & 7) * 768 + 5 * 128)->x;
            while (true) {
                uint32_t t, v0[24], v1[24];
                asm volatile("ld.relaxed.gpu.global.u32 %0, [%1];" : "=r"(t) : "l"(poll) : "memory");
                const int c0 = __ffs(ready) - 1, c1 = __ffs(ready & (ready - 1)) - 1;
                if (c0 >= 0) ld_part(v0, src + c0 * 768);
                if (c1 >= 0) ld_part(v1, src + c1 * 768);
                if (!pending) mbar_wait(sb + OFF_OWN, 0);
                if (!own_done && (!pending || __all_sync(0xffffffffu, mbar_test(sb + OFF_OWN, 0)))) {
                    own_done = true;
#pragma unroll
                    for (int j = 0; j < 12; j++) {
                        float4 v;
                        asm volatile("ld.shared.v4.f32 {%0, %1, %2, %3}, [%4];" : "=f"(v.x), "=f"(v.y), "=f"(v.z), "=f"(v.w) : "r"(own + j * 2048) : "memory");
                        acc[4 * j] += v.x; acc[4 * j + 1] += v.y; acc[4 * j + 2] += v.z; acc[4 * j + 3] += v.w;
                    }
                }
                if (c0 >= 0 && add_part(acc, v0, tag)) pending &= ~(1u << c0);
                if (c1 >= 0 && add_part(acc, v1, tag)) pending &= ~(1u << c1);
                if (++n > SPIN_LIMIT) pending = 0;
                if (!pending && own_done) break;
                ready = __ballot_sync(0xffffffffu, ((t ^ tag) & 1) == 0) & pending;
                if (__popc(pending) <= 2) ready = pending;
            }
            const uint32_t st = sb + OFF_RING + 4 * UNIT + wl * 3072;
            {
                const int i = lane & 7, mh = (lane >> 3) & 1, jo = lane >> 4;
                const uint32_t base = st + jo * 256 + i * 32 + ((mh ^ (i >> 2)) << 4);
#pragma unroll
                for (int j = 0; j < 12; j += 2)
                    stsm4t(base + j * 256, pack_bf16(acc[4 * j], acc[4 * j + 1]), pack_bf16(acc[4 * j + 2], acc[4 * j + 3]),
                           pack_bf16(acc[4 * j + 4], acc[4 * j + 5]), pack_bf16(acc[4 * j + 6], acc[4 * j + 7]));
            }
            __syncwarp();
#pragma unroll
            for (int u = 0; u < 6; u++) {
                const int nrow = u * 16 + (lane >> 1), c = lane & 1;
                uint4 v;
                asm volatile("ld.shared.v4.u32 {%0, %1, %2, %3}, [%4];" : "=r"(v.x), "=r"(v.y), "=r"(v.z), "=r"(v.w)
                             : "r"(st + nrow * 32 + ((c ^ ((nrow >> 2) & 1)) << 4)) : "memory");
                const int row = bp * 96 + ((nrow >> 3) & 1) * 48 + (nrow >> 4) * 8 + (nrow & 7);
                *reinterpret_cast<uint4*>(out + (size_t)row * 1024 + br * 512 + hkv * 64 + wl * 16 + c * 8) = v;
            }
        }
    }
}

typedef CUresult (*EncodeFn)(CUtensorMap*, CUtensorMapDataType, cuuint32_t, void*, const cuuint64_t*, const cuuint64_t*,
                             const cuuint32_t*, const cuuint32_t*, CUtensorMapInterleave, CUtensorMapSwizzle,
                             CUtensorMapL2promotion, CUtensorMapFloatOOBfill);

void make_map(EncodeFn enc, CUtensorMap* m, const void* ptr, uint64_t rows, uint64_t cols, uint32_t brows, uint32_t bchunks,
              CUtensorMapL2promotion promo = CU_TENSOR_MAP_L2_PROMOTION_L2_256B) {
    cuuint64_t dims[3] = {64, rows, cols / 64};
    cuuint64_t strides[2] = {cols * 2, 128};
    cuuint32_t box[3] = {64, brows, bchunks};
    cuuint32_t es[3] = {1, 1, 1};
    enc(m, CU_TENSOR_MAP_DATA_TYPE_BFLOAT16, 3, const_cast<void*>(ptr), dims, strides, box, es, CU_TENSOR_MAP_INTERLEAVE_NONE,
        CU_TENSOR_MAP_SWIZZLE_128B, promo, CU_TENSOR_MAP_FLOAT_OOB_FILL_NONE);
}

}

extern "C" void kernel_launch(void* const* d_in, const int* in_sizes, int n_in, void* d_out, int out_size) {
    (void)in_sizes; (void)n_in; (void)out_size;
    static EncodeFn enc = nullptr;
    if (!enc) {
        void* fn = nullptr;
        cudaDriverEntryPointQueryResult st;
        cudaGetDriverEntryPoint("cuTensorMapEncodeTiled", &fn, cudaEnableDefault, &st);
        enc = (EncodeFn)fn;
        cudaFuncSetAttribute(gqa_fused_kernel, cudaFuncAttributeMaxDynamicSharedMemorySize, SMEM_BYTES);
    }
    Params P;
    for (int br = 0; br < 2; br++) {
        make_map(enc, &P.x[br],  d_in[br * 5 + 0], 768, 512, 96, 2);
        make_map(enc, &P.k[br],  d_in[br * 5 + 1], 16 * 8 * 1024, 128, 128, 2, CU_TENSOR_MAP_L2_PROMOTION_L2_128B);
        make_map(enc, &P.v[br],  d_in[br * 5 + 2], 16 * 8 * 1024, 128, 128, 2, CU_TENSOR_MAP_L2_PROMOTION_L2_128B);
        make_map(enc, &P.wq[br], d_in[br * 5 + 3], 512, 4096, 128, 1);
        make_map(enc, &P.wo[br], d_in[br * 5 + 4], 4096, 512, 128, 1);
        P.kp[br] = (const uint8_t*)d_in[br * 5 + 1];
        P.vp[br] = (const uint8_t*)d_in[br * 5 + 2];
    }
    gqa_fused_kernel<<<128, NTHREADS, SMEM_BYTES>>>(P, (__nv_bfloat16*)d_out);
}
```
